```python
import torch

def _softmax(x, axis=-1):
    return torch.softmax(x, dim=axis)
def _gelu(x):
    return torch.nn.functional.gelu(x, approximate="tanh")
def _silu(x):
    return torch.nn.functional.silu(x)
def _sigmoid(x):
    return torch.sigmoid(x)
def _layernorm(x, axis=-1, eps=1e-5):
    m = x.mean(dim=axis, keepdim=True)
    v = x.var(dim=axis, keepdim=True, unbiased=False)
    return (x - m) / torch.sqrt(v + eps)
def _scatter_add(tgt, idx, src, axis=0):
    return tgt.clone().index_add_(axis, idx, src)
def _segment_sum(src, seg, n):
    out = torch.zeros((n,) + src.shape[1:], dtype=src.dtype)
    return out.index_add_(0, seg, src)
def _pad(x, pw):
    flat = tuple(v for pair in reversed(pw) for v in pair)
    return torch.nn.functional.pad(x, flat)

kernel_name = 'standalone__gqa_block_cached__decode'

def setup_inputs():

    _w = (lambda a: (lambda t: t.to(torch.bfloat16) if t.is_floating_point() else t)(torch.as_tensor(a)))
    B, Sq, D = 8, 1, 512
    Hq, Hkv, Sk, Dh = 32, 8, 4096, 128
    assert Hq % Hkv == 0, (Hq, Hkv)
    return {
        "x": _w((lambda *s: torch.randn(*s, dtype=torch.bfloat16) * 0.8)(B, Sq, D)),
        "k_cache": _w((lambda *s: torch.randn(*s, dtype=torch.bfloat16) * 0.8)(B, Hkv, Sk, Dh)),
        "v_cache": _w((lambda *s: torch.randn(*s, dtype=torch.bfloat16) * 0.05)(B, Hkv, Sk, Dh)),
        "wq": _w((lambda *s: torch.randn(*s, dtype=torch.bfloat16) * 0.8)(D, Hq * Dh) * (D ** -0.5)),
        "wo": _w((lambda *s: torch.randn(*s, dtype=torch.bfloat16) * 0.05)(Hq * Dh, D) * ((Hq * Dh) ** -0.5)),
    }

def reference(x, k_cache, v_cache, wq, wo):
    B, Sq, D = x.shape
    Hq, Dh = 32, 128
    Hkv = k_cache.shape[1]
    rep = Hq // Hkv
    q = (lambda x, *d: x.permute(*d))((x @ wq).reshape(B, Sq, Hq, Dh), 0, 2, 1, 3)
    k = (lambda x, n, axis: torch.repeat_interleave(x, n, dim=axis))(k_cache, rep, axis=1)
    v = (lambda x, n, axis: torch.repeat_interleave(x, n, dim=axis))(v_cache, rep, axis=1)
    scores = torch.einsum("bhqd,bhkd->bhqk", q, k) * (Dh ** -0.5)
    p = _softmax(scores, axis=-1)
    o = torch.einsum("bhqk,bhkd->bhqd", p, v)
    return (lambda x, *d: x.permute(*d))(o, 0, 2, 1, 3).reshape(B, Sq, Hq * Dh) @ wo
```

```cpp
#include <cuda_runtime.h>
#include <cuda_bf16.h>
#include <cuda.h>
#include <stdint.h>

namespace {

constexpr int kB = 8, kHkv = 8, kSk = 4096, kDh = 128, kD = 512;
constexpr int kWarps = 8;
constexpr int kThreads = 320;
constexpr int kTileKeys = 32;
constexpr int kTileBytes = kTileKeys * 256;
constexpr int kStages = 3;
constexpr int kSlots = kWarps * kStages;
constexpr int kIters = 2048 / (kWarps * kTileKeys);
constexpr int kSeq = 2 * kIters + 2;
constexpr int kWTileBytes = 64 * 64;
#define GQA_TAU 327
#define GQA_OFF 200
#define GQA_C0 300
constexpr uint32_t kTau = GQA_TAU, kOff = GQA_OFF, kC0 = GQA_C0;
constexpr uint32_t kPrefetchBytes = 8192;

constexpr int kOffRing = 0;
constexpr int kOffCml = kSlots * kTileBytes;
constexpr int kOffRed = kOffCml + 512;
constexpr int kOffQs = kOffRed + 9216;
constexpr int kOffBar = kOffQs + 1024;
constexpr int kOffSched = kOffBar + 56 * 8;
constexpr int kSmemBytes = kOffBar + 64 * 8 + 1024;

constexpr unsigned kSpinLimit = 1u << 24;

}

__device__ __align__(128) unsigned int g_done;
__device__ __align__(128) unsigned long long g_qll[8 * 8 * 256];
__device__ __align__(128) unsigned int g_o[2 * 8 * 8 * 2 * 256];
__device__ __align__(128) unsigned long long g_zf;

namespace {

__device__ __forceinline__ uint32_t smem_u32(const void* p) { return (uint32_t)__cvta_generic_to_shared(p); }
__device__ __forceinline__ void mbar_init(uint32_t bar, uint32_t cnt) {
    asm volatile("mbarrier.init.shared::cta.b64 [%0], %1;" ::"r"(bar), "r"(cnt) : "memory");
}
__device__ __forceinline__ void mbar_expect_tx(uint32_t bar, uint32_t bytes) {
    asm volatile("mbarrier.arrive.expect_tx.shared::cta.b64 _, [%0], %1;" ::"r"(bar), "r"(bytes) : "memory");
}
__device__ __forceinline__ void mbar_arrive(uint32_t bar) {
    asm volatile("mbarrier.arrive.shared::cta.b64 _, [%0];" ::"r"(bar) : "memory");
}
__device__ __forceinline__ void mbar_wait(uint32_t bar, uint32_t parity) {
    uint32_t done;
    unsigned it = 0;
    do {
        asm volatile(
            "{ .reg .pred p; mbarrier.try_wait.parity.shared::cta.b64 p, [%1], %2; selp.u32 %0, 1, 0, p; }"
            : "=r"(done) : "r"(bar), "r"(parity) : "memory");
        if (++it > kSpinLimit) __trap();
    } while (!done);
}
__device__ __forceinline__ void mbar_wait_cluster(uint32_t bar, uint32_t parity) {
    uint32_t done;
    unsigned it = 0;
    do {
        asm volatile(
            "{ .reg .pred p; mbarrier.try_wait.parity.acquire.cluster.shared::cta.b64 p, [%1], %2; selp.u32 %0, 1, 0, p; }"
            : "=r"(done) : "r"(bar), "r"(parity) : "memory");
        if (++it > kSpinLimit) __trap();
    } while (!done);
}
__device__ __forceinline__ void tma_2d(uint32_t dst, const CUtensorMap* tm, int c0, int c1, uint32_t bar, uint64_t pol) {
    asm volatile(
        "cp.async.bulk.tensor.2d.shared::cluster.global.mbarrier::complete_tx::bytes.L2::cache_hint [%0], [%1, {%3, %4}], [%2], %5;"
        ::"r"(dst), "l"(tm), "r"(bar), "r"(c0), "r"(c1), "l"(pol) : "memory");
}
__device__ __forceinline__ uint32_t now_ns() {
    uint32_t t;
    asm volatile("mov.u32 %0, %%globaltimer_lo;" : "=r"(t) :: "memory");
    return t;
}
__device__ __forceinline__ void ldsm_x4(uint32_t (&r)[4], uint32_t addr) {
    asm volatile("ldmatrix.sync.aligned.m8n8.x4.shared.b16 {%0,%1,%2,%3}, [%4];"
                 : "=r"(r[0]), "=r"(r[1]), "=r"(r[2]), "=r"(r[3]) : "r"(addr) : "memory");
}
__device__ __forceinline__ void ldsm_x4_t(uint32_t (&r)[4], uint32_t addr) {
    asm volatile("ldmatrix.sync.aligned.m8n8.x4.trans.shared.b16 {%0,%1,%2,%3}, [%4];"
                 : "=r"(r[0]), "=r"(r[1]), "=r"(r[2]), "=r"(r[3]) : "r"(addr) : "memory");
}
__device__ __forceinline__ void mma_bf16(float (&d)[4], const uint32_t (&a)[4], uint32_t b0, uint32_t b1) {
    asm volatile(
        "mma.sync.aligned.m16n8k16.row.col.f32.bf16.bf16.f32 {%0,%1,%2,%3}, {%4,%5,%6,%7}, {%8,%9}, {%0,%1,%2,%3};"
        : "+f"(d[0]), "+f"(d[1]), "+f"(d[2]), "+f"(d[3])
        : "r"(a[0]), "r"(a[1]), "r"(a[2]), "r"(a[3]), "r"(b0), "r"(b1));
}
__device__ __forceinline__ uint32_t movmatrix_t(uint32_t a) {
    uint32_t d;
    asm volatile("movmatrix.sync.aligned.m8n8.trans.b16 %0, %1;" : "=r"(d) : "r"(a));
    return d;
}
__device__ __forceinline__ uint32_t pack_bf16(float lo, float hi) {
    uint32_t r;
    asm("cvt.rn.bf16x2.f32 %0, %1, %2;" : "=r"(r) : "f"(hi), "f"(lo));
    return r;
}
__device__ __forceinline__ float ex2(float x) {
    float y;
    asm("ex2.approx.ftz.f32 %0, %1;" : "=f"(y) : "f"(x));
    return y;
}
__device__ __forceinline__ void st_ll(unsigned long long* p, uint32_t data, uint32_t flag) {
    unsigned long long v = ((unsigned long long)flag << 32) | data;
    asm volatile("st.relaxed.gpu.global.u64 [%0], %1;" ::"l"(p), "l"(v) : "memory");
}
__device__ __forceinline__ unsigned long long ld_ll(const unsigned long long* p) {
    unsigned long long v;
    asm volatile("ld.relaxed.gpu.global.u64 %0, [%1];" : "=l"(v) : "l"(p) : "memory");
    return v;
}
__device__ __forceinline__ void st_relaxed_v4(unsigned int* p, uint32_t a, uint32_t b, uint32_t c, uint32_t d) {
    asm volatile("st.relaxed.gpu.global.v4.u32 [%0], {%1,%2,%3,%4};" ::"l"(p), "r"(a), "r"(b), "r"(c), "r"(d) : "memory");
}
__device__ __forceinline__ void st_relaxed_u32_if(bool p, unsigned int* ptr, uint32_t a) {
    asm volatile("{ .reg .pred p; setp.ne.u32 p, %2, 0; @p st.relaxed.gpu.global.u32 [%0], %1; }"
                 ::"l"(ptr), "r"(a), "r"((uint32_t)p) : "memory");
}
__device__ __forceinline__ void red_add_bf16x2_if(bool p, __nv_bfloat16* ptr, uint32_t v) {
    asm volatile("{ .reg .pred p; setp.ne.u32 p, %2, 0; @p red.relaxed.gpu.global.add.noftz.bf16x2 [%0], %1; }"
                 ::"l"(ptr), "r"(v), "r"((uint32_t)p) : "memory");
}
__device__ __forceinline__ void sts_v4(uint32_t addr, float a, float b, float c, float d) {
    asm volatile("st.shared.v4.f32 [%0], {%1,%2,%3,%4};" ::"r"(addr), "f"(a), "f"(b), "f"(c), "f"(d) : "memory");
}
__device__ __forceinline__ void ld_relaxed_v4_if(bool p, uint4& v, const unsigned int* ptr) {
    asm volatile("{ .reg .pred p; setp.ne.u32 p, %5, 0; @p ld.relaxed.gpu.global.v4.u32 {%0,%1,%2,%3}, [%4]; }"
                 : "+r"(v.x), "+r"(v.y), "+r"(v.z), "+r"(v.w) : "l"(ptr), "r"((uint32_t)p) : "memory");
}
__device__ __forceinline__ bool o_valid(const uint4& v) { return min(min(v.x, v.y), min(v.z, v.w)) != 0u; }
__device__ __forceinline__ uint32_t add_bf16x2(uint32_t a, uint32_t b) {
    uint32_t d;
    asm("add.rn.bf16x2 %0, %1, %2;" : "=r"(d) : "r"(a), "r"(b));
    return d;
}
__device__ __forceinline__ uint4 lds_v4(uint32_t addr) {
    uint4 v;
    asm volatile("ld.shared.v4.u32 {%0,%1,%2,%3}, [%4];" : "=r"(v.x), "=r"(v.y), "=r"(v.z), "=r"(v.w) : "r"(addr) : "memory");
    return v;
}
__device__ __forceinline__ uint32_t ld_relaxed_u32(const unsigned int* p) {
    uint32_t v;
    asm volatile("ld.relaxed.gpu.global.u32 %0, [%1];" : "=r"(v) : "l"(p) : "memory");
    return v;
}
__device__ __forceinline__ uint32_t mapa(uint32_t addr, uint32_t rank) {
    uint32_t r;
    asm("mapa.shared::cluster.u32 %0, %1, %2;" : "=r"(r) : "r"(addr), "r"(rank));
    return r;
}
__device__ __forceinline__ void st_async_v4(uint32_t addr, float a, float b, float c, float d, uint32_t bar) {
    asm volatile("st.async.weak.shared::cluster.mbarrier::complete_tx::bytes.v4.f32 [%0], {%1,%2,%3,%4}, [%5];"
                 ::"r"(addr), "f"(a), "f"(b), "f"(c), "f"(d), "r"(bar) : "memory");
}
__device__ __forceinline__ bool elect_one() {
    uint32_t pred;
    asm volatile("{ .reg .pred P; elect.sync _|P, 0xffffffff; selp.b32 %0, 1, 0, P; }" : "=r"(pred));
    return pred != 0;
}
__device__ __forceinline__ void bar_consumers() { asm volatile("bar.sync 1, 256;" ::: "memory"); }

__global__ void __cluster_dims__(2, 1, 1) __launch_bounds__(kThreads, 1)
gqa_decode_kernel(const __grid_constant__ CUtensorMap tmK, const __grid_constant__ CUtensorMap tmV,
                  const __grid_constant__ CUtensorMap tmWq, const __grid_constant__ CUtensorMap tmWo,
                  const __nv_bfloat16* __restrict__ x, const __nv_bfloat16* __restrict__ kc, __nv_bfloat16* __restrict__ out) {
    extern __shared__ uint8_t smem_raw[];
    uint32_t sbase = (smem_u32(smem_raw) + 1023u) & ~1023u;
    asm volatile("" : "+r"(sbase));
    uint8_t* sgen = smem_raw + (sbase - smem_u32(smem_raw));

    const int tid = threadIdx.x, lane = tid & 31;
    const int warp = __shfl_sync(0xffffffffu, tid >> 5, 0);
    if (blockIdx.x < 2) {
        if (blockIdx.x == 0) {
            const uint32_t t0 = now_ns();
            const uint32_t epoch_raw = ld_relaxed_u32(&g_done);
            if (tid < 256) {
                st_relaxed_v4(reinterpret_cast<unsigned int*>(out) + tid * 8, 0u, 0u, 0u, 0u);
                st_relaxed_v4(reinterpret_cast<unsigned int*>(out) + tid * 8 + 4, 0u, 0u, 0u, 0u);
            }
            __syncthreads();
            if (tid == 0)
                asm volatile("st.release.gpu.global.u64 [%0], %1;" ::"l"(&g_zf), "l"(((unsigned long long)t0 << 32) | ((epoch_raw >> 7) + 1u)) : "memory");
        }
        return;
    }
    const int cta = blockIdx.x - 2;
    const int r = cta & 1, pair = cta >> 1, b = pair >> 3, g = pair & 7;
    const int slice = b * 2 + r;
    const int gq = lane >> 2, t = lane & 3;
    if (tid == kThreads - 32)
        asm volatile("cp.async.bulk.prefetch.L2.global [%0], %1;" ::"l"(kc + (size_t)(pair * kSk + r * 2048) * kDh), "r"(kPrefetchBytes) : "memory");

    const uint32_t bar_full = sbase + kOffBar;
    const uint32_t bar_empty = bar_full + kSlots * 8;
    const uint32_t bar_ml = bar_empty + kSlots * 8;
    const uint32_t bar_z = bar_ml + 8;
    const uint32_t ring = sbase + kOffRing;
    volatile uint32_t* const sched = reinterpret_cast<volatile uint32_t*>(sgen + kOffSched);

    static_assert(2 * kSlots + 2 == 5 * (kThreads / 32), "barrier initialisation");
    if (elect_one()) {
        if (warp >= kWarps - 2) {
            const CUtensorMap* tm = warp == kWarps ? &tmWq : warp == kWarps + 1 ? &tmK : warp == kWarps - 1 ? &tmV : &tmWo;
            asm volatile("prefetch.tensormap [%0];" ::"l"(tm) : "memory");
        }
#pragma unroll
        for (int i = 0; i < 5; i++) mbar_init(bar_full + (warp * 5 + i) * 8, 1);
        asm volatile("fence.mbarrier_init.release.cluster;" ::: "memory");
    }
    __syncthreads();
    if (warp < kWarps) {
        const uint32_t my_full = bar_full + warp * (kStages * 8), my_empty = bar_empty + warp * (kStages * 8);
        const uint32_t my_ring = ring + warp * (kStages * kTileBytes);
        uint4 xv[2];
        {
            const __nv_bfloat16* xp = x + gq * 512 + warp * 64 + t * 16;
#pragma unroll
            for (int i = 0; i < 2; i++)
                asm volatile("ld.global.nc.v4.u32 {%0,%1,%2,%3}, [%4];"
                             : "=r"(xv[i].x), "=r"(xv[i].y), "=r"(xv[i].z), "=r"(xv[i].w) : "l"(xp + i * 8));
        }
        const uint32_t epoch_raw = ld_relaxed_u32(&g_done);

        unsigned long long* const q_pub = &g_qll[(g * 8 + (tid >> 4)) * 256 + slice * 16 + (tid & 15)];
        unsigned int* const o_cta = &g_o[((g * 8 + b) * 2 + r) * 256];
        {
            if (tid < 128) st_ll(q_pub, 0u, 0u);
            if (tid < 128) st_relaxed_v4(o_cta + (tid >> 6) * 32768 + (tid & 63) * 4, 0u, 0u, 0u, 0u);
        }
        if (tid == 0) mbar_expect_tx(bar_ml, 32 * 16);
        __syncwarp();
        asm volatile("barrier.cluster.arrive.relaxed.aligned;" ::: "memory");

        const uint32_t flag = (epoch_raw >> 7) + 1u;

        {
            float d[2][4] = {{0.f, 0.f, 0.f, 0.f}, {0.f, 0.f, 0.f, 0.f}};
            const uint32_t xw[8] = {xv[0].x, xv[0].y, xv[0].z, xv[0].w, xv[1].x, xv[1].y, xv[1].z, xv[1].w};
            mbar_wait(my_full, 0);
            const uint32_t wt = my_ring;
            const int kl = lane & 7;
#pragma unroll
            for (int s = 0; s < 4; s++) {
                const int row = (kl >> 1) * 16 + 4 * s + 2 * (lane >> 4) + (kl & 1);
#pragma unroll
                for (int cm = 0; cm < 2; cm++) {
                    const int chunk = 2 * cm + ((lane >> 3) & 1);
                    uint32_t a[4];
                    ldsm_x4_t(a, wt + row * 64 + ((chunk ^ ((row >> 1) & 3)) << 4));
                    mma_bf16(d[cm], a, xw[2 * s], xw[2 * s + 1]);
                }
            }
            float* red = reinterpret_cast<float*>(sgen + kOffRed);
#pragma unroll
            for (int cm = 0; cm < 2; cm++)
#pragma unroll
                for (int j = 0; j < 4; j++)
                    red[(warp * 8 + 2 * t + (j & 1)) * 36 + cm * 16 + (j >> 1) * 8 + gq] = d[cm][j];
            __syncwarp();
            if (lane == 0) mbar_arrive(my_empty);
            bar_consumers();
            if (tid < 128) {
                const float2* red2 = reinterpret_cast<const float2*>(sgen + kOffRed);
                float sx = 0.f, sy = 0.f;
#pragma unroll
                for (int w = 0; w < kWarps; w++) {
                    const float2 v = red2[(w * 8 + (tid >> 4)) * 18 + (tid & 15)];
                    sx += v.x;
                    sy += v.y;
                }
                st_ll(q_pub, pack_bf16(sx, sy), flag);
            }
            {
                const unsigned long long* qp = &g_qll[(g * 8 + b) * 256 + tid];
                unsigned long long v = ld_ll(qp);
                unsigned it = 0;
                while ((uint32_t)(v >> 32) != flag) {
                    __nanosleep(64);
                    v = ld_ll(qp);
                    if (++it > kSpinLimit) __trap();
                }
                reinterpret_cast<uint32_t*>(sgen + kOffQs)[tid] = (uint32_t)v;
            }
            bar_consumers();
        }
        uint32_t qf[8][2];
        {
            const uint32_t* qs = reinterpret_cast<const uint32_t*>(sgen + kOffQs);
#pragma unroll
            for (int ks = 0; ks < 8; ks++) {
                qf[ks][0] = qs[(gq & 3) * 64 + ks * 8 + t];
                qf[ks][1] = qs[(gq & 3) * 64 + ks * 8 + 4 + t];
            }
        }
        asm volatile("barrier.cluster.wait.aligned;" ::: "memory");

        const int krow = (lane & 7) + ((lane >> 3) & 1) * 8, vrow = (lane & 7) + (lane >> 4) * 8;
        const uint32_t koff = krow * 256, kx = ((lane >> 4) ^ ((2 * krow) & 7)) << 4;
        const uint32_t voff = vrow * 256, vx = (((lane >> 3) & 1) ^ ((2 * vrow) & 7)) << 4;
        auto tile_off = [&](uint32_t rowoff, uint32_t xr, int c2, int blk) -> uint32_t {
            return rowoff + blk * 4096 + (c2 >> 2) * 128 + (xr ^ ((((2 * c2) & 7) ^ (c2 >> 2)) << 4));
        };

        constexpr float kScale = 0.08838834764831845f * 1.4426950408889634f;
        float o[8][4];
#pragma unroll
        for (int i = 0; i < 8; i++) { o[i][0] = o[i][1] = o[i][2] = o[i][3] = 0.f; }
        float m0 = -INFINITY, m1 = -INFINITY, l0 = 0.f, l1 = 0.f;
        uint32_t stage = 1, par = 0;

#pragma unroll 1
        for (int it = 0; it < kIters; it++) {
            mbar_wait(my_full + stage * 8, par);
            uint32_t tb = my_ring + stage * kTileBytes;
            float s[2][4];
#pragma unroll
            for (int mt = 0; mt < 2; mt++) {
                float sa[4] = {0.f, 0.f, 0.f, 0.f}, sb[4] = {0.f, 0.f, 0.f, 0.f};
#pragma unroll
                for (int ks = 0; ks < 8; ks += 2) {
                    uint32_t a[4], a2[4];
                    ldsm_x4(a, tb + tile_off(koff, kx, ks, mt));
                    ldsm_x4(a2, tb + tile_off(koff, kx, ks + 1, mt));
                    mma_bf16(sa, a, qf[ks][0], qf[ks][1]);
                    mma_bf16(sb, a2, qf[ks + 1][0], qf[ks + 1][1]);
                }
#pragma unroll
                for (int j = 0; j < 4; j++) s[mt][j] = sa[j] + sb[j];
            }
            __syncwarp();
            if (lane == 0) mbar_arrive(my_empty + stage * 8);
            if (++stage == kStages) { stage = 0; par ^= 1; }

            float mx0 = fmaxf(fmaxf(s[0][0], s[0][2]), fmaxf(s[1][0], s[1][2]));
            float mx1 = fmaxf(fmaxf(s[0][1], s[0][3]), fmaxf(s[1][1], s[1][3]));
#pragma unroll
            for (int d = 4; d <= 16; d <<= 1) {
                mx0 = fmaxf(mx0, __shfl_xor_sync(0xffffffffu, mx0, d));
                mx1 = fmaxf(mx1, __shfl_xor_sync(0xffffffffu, mx1, d));
            }
            const float mn0 = fmaxf(m0, mx0), mn1 = fmaxf(m1, mx1);
            const float sc0 = ex2((m0 - mn0) * kScale), sc1 = ex2((m1 - mn1) * kScale);
            m0 = mn0;
            m1 = mn1;
            const float mb0 = mn0 * kScale, mb1 = mn1 * kScale;
            float p[2][4];
#pragma unroll
            for (int mt = 0; mt < 2; mt++) {
                p[mt][0] = ex2(fmaf(s[mt][0], kScale, -mb0));
                p[mt][1] = ex2(fmaf(s[mt][1], kScale, -mb1));
                p[mt][2] = ex2(fmaf(s[mt][2], kScale, -mb0));
                p[mt][3] = ex2(fmaf(s[mt][3], kScale, -mb1));
            }
            l0 = l0 * sc0 + ((p[0][0] + p[0][2]) + (p[1][0] + p[1][2]));
            l1 = l1 * sc1 + ((p[0][1] + p[0][3]) + (p[1][1] + p[1][3]));
            float os0 = sc0, os1 = sc1;
            if (it == kIters - 1) {
#pragma unroll
                for (int d = 4; d <= 16; d <<= 1) {
                    l0 += __shfl_xor_sync(0xffffffffu, l0, d);
                    l1 += __shfl_xor_sync(0xffffffffu, l1, d);
                }
                const int sl = r * 8 + warp;
                if (t < 2 && gq < 2)
                    st_async_v4(mapa(sbase + kOffCml + (t * 16 + sl) * 16, gq), m0, l0, m1, l1, mapa(bar_ml, gq));
                mbar_wait_cluster(bar_ml, 0);
                const float4 ml = reinterpret_cast<const float4*>(sgen + kOffCml)[lane];
                float M0 = ml.x, M1 = ml.z;
#pragma unroll
                for (int d = 1; d <= 8; d <<= 1) {
                    M0 = fmaxf(M0, __shfl_xor_sync(0xffffffffu, M0, d));
                    M1 = fmaxf(M1, __shfl_xor_sync(0xffffffffu, M1, d));
                }
                const float e0 = ex2((ml.x - M0) * kScale), e1 = ex2((ml.z - M1) * kScale);
                float L0 = e0 * ml.y, L1 = e1 * ml.w;
#pragma unroll
                for (int d = 1; d <= 8; d <<= 1) {
                    L0 += __shfl_xor_sync(0xffffffffu, L0, d);
                    L1 += __shfl_xor_sync(0xffffffffu, L1, d);
                }
                const float f0 = __shfl_sync(0xffffffffu, e0 / L0, (t & 1) * 16 + sl);
                const float f1 = __shfl_sync(0xffffffffu, e1 / L1, (t & 1) * 16 + sl);
                os0 *= f0;
                os1 *= f1;
#pragma unroll
                for (int mt = 0; mt < 2; mt++) {
                    p[mt][0] *= f0; p[mt][1] *= f1; p[mt][2] *= f0; p[mt][3] *= f1;
                }
            }
            uint32_t pb[2][2];
#pragma unroll
            for (int mt = 0; mt < 2; mt++) {
                pb[mt][0] = movmatrix_t(pack_bf16(p[mt][0], p[mt][1]));
                pb[mt][1] = movmatrix_t(pack_bf16(p[mt][2], p[mt][3]));
            }
#pragma unroll
            for (int i = 0; i < 8; i++) {
                o[i][0] *= os0; o[i][1] *= os1; o[i][2] *= os0; o[i][3] *= os1;
            }

            if (it == kIters - 1) {
                const uint32_t xb = my_ring + ((kSeq - 3) % kStages) * kTileBytes;
                if (t < 2) {
#pragma unroll
                    for (int i = 0; i < 8; i++) sts_v4(xb + i * 256 + (gq * 2 + t) * 16, o[i][0], o[i][1], o[i][2], o[i][3]);
                }
                sts_v4(xb + 2048 + lane * 16, __uint_as_float(pb[0][0]), __uint_as_float(pb[0][1]),
                       __uint_as_float(pb[1][0]), __uint_as_float(pb[1][1]));
                break;
            }

            mbar_wait(my_full + stage * 8, par);
            tb = my_ring + stage * kTileBytes;
#pragma unroll
            for (int kt = 0; kt < 2; kt++) {
#pragma unroll
                for (int dm = 0; dm < 8; dm++) {
                    uint32_t a[4];
                    ldsm_x4_t(a, tb + tile_off(voff, vx, dm, kt));
                    mma_bf16(o[dm], a, pb[kt][0], pb[kt][1]);
                }
            }
            __syncwarp();
            if (lane == 0) mbar_arrive(my_empty + stage * 8);
            if (++stage == kStages) { stage = 0; par ^= 1; }
        }
        bar_consumers();

        float oa[4] = {0.f, 0.f, 0.f, 0.f}, ob[4] = {0.f, 0.f, 0.f, 0.f};
        uint4 pw[kWarps];
        {
            const uint32_t xb = ring + ((kSeq - 3) % kStages) * kTileBytes;
#pragma unroll
            for (int w = 0; w < kWarps; w++) {
                const uint4 v = lds_v4(xb + w * (kStages * kTileBytes) + warp * 256 + (gq * 2 + (t & 1)) * 16);
                oa[0] += __uint_as_float(v.x); oa[1] += __uint_as_float(v.y);
                oa[2] += __uint_as_float(v.z); oa[3] += __uint_as_float(v.w);
                pw[w] = lds_v4(xb + w * (kStages * kTileBytes) + 2048 + lane * 16);
            }
        }
        mbar_wait(bar_z, 0);
        uint32_t live = 0;
#pragma unroll 1
        for (;;) {
            asm volatile("" : "+r"(live));
            if (live) {
                constexpr int kVStage = (kSeq - 2) % kStages, kVPar = ((kSeq - 2) / kStages) & 1;
                const uint32_t voffw = tile_off(voff, vx, warp, 0), vblk = 4096;
#pragma unroll
                for (int w = 0; w < kWarps; w++) {
                    mbar_wait(bar_full + (w * kStages + kVStage) * 8, kVPar);
                    const uint32_t vt = ring + (w * kStages + kVStage) * kTileBytes + voffw;
                    uint32_t a[4], a2[4];
                    ldsm_x4_t(a, vt);
                    ldsm_x4_t(a2, vt + vblk);
                    mma_bf16(oa, a, pw[w].x, pw[w].y);
                    mma_bf16(ob, a2, pw[w].z, pw[w].w);
                }
            }
            {
                const bool odd = gq & 1;
                const float ca = t < 2 ? oa[0] + ob[0] : oa[1] + ob[1], cb = t < 2 ? oa[2] + ob[2] : oa[3] + ob[3];
                const float cx = __shfl_xor_sync(0xffffffffu, odd ? ca : cb, 4);
                const uint32_t w0 = ~pack_bf16(odd ? cx : ca, odd ? cb : cx);
                unsigned int* op = o_cta + (flag & 1) * 32768 + warp * 32 + ((t & 1) * 2 + (t >> 1)) * 8 + (gq & 1) * 4 + (((gq >> 1) - 2 * warp - (gq & 1)) & 3);
                st_relaxed_u32_if(live, op, w0);
            }
            uint4 u[4];
#pragma unroll
            for (int c = 0; c < 4; c++) u[c] = make_uint4(0u, 0u, 0u, 0u);
            const unsigned int* op = &g_o[(flag & 1) * 32768 + (g * 8 + gq) * 512 + ((warp & 1) * 4 + (t >> 1)) * 32 + (warp >> 1) * 8 + (t & 1) * 4];
            constexpr int kWoStage = (kSeq - 1) % kStages, kWoPar = ((kSeq - 1) / kStages) & 1;
            if (live) mbar_wait(my_full + kWoStage * 8, kWoPar);
            for (unsigned it = 0;; it++) {
#pragma unroll
                for (int c = 0; c < 4; c++)
                    ld_relaxed_v4_if(live && !o_valid(u[c]), u[c], op + (c >> 1) * 256 + (c & 1) * 64);
                const bool all = o_valid(u[0]) && o_valid(u[1]) && o_valid(u[2]) && o_valid(u[3]);
                if (__all_sync(0xffffffffu, all || !live)) break;
                if (it > kSpinLimit) __trap();
            }
            const uint32_t b0[4] = {add_bf16x2(~u[0].x, ~u[2].x), add_bf16x2(~u[0].y, ~u[2].y), add_bf16x2(~u[0].z, ~u[2].z), add_bf16x2(~u[0].w, ~u[2].w)};
            const uint32_t b1[4] = {add_bf16x2(~u[1].x, ~u[3].x), add_bf16x2(~u[1].y, ~u[3].y), add_bf16x2(~u[1].z, ~u[3].z), add_bf16x2(~u[1].w, ~u[3].w)};
            const uint32_t wt = my_ring + kWoStage * kTileBytes;
            const int drow = (lane >> 4) * 32 + (lane & 6) * 4 + (lane & 1), drot = (lane & 7) >> 1;
            float d[2][4], e[2][4];
#pragma unroll
            for (int cm = 0; cm < 2; cm++)
#pragma unroll
                for (int j = 0; j < 4; j++) d[cm][j] = e[cm][j] = 0.f;
#pragma unroll
            for (int s = 0; s < 4; s++) {
                const int row = drow + 2 * ((s + drot) & 3);
#pragma unroll
                for (int cm = 0; cm < 2; cm++) {
                    const int chunk = 2 * cm + ((lane >> 3) & 1);
                    uint32_t a[4];
                    ldsm_x4_t(a, wt + row * 64 + ((chunk ^ ((row >> 1) & 3)) << 4));
                    mma_bf16((s & 1) ? e[cm] : d[cm], a, b0[s], b1[s]);
                }
            }
#pragma unroll
            for (int cm = 0; cm < 2; cm++)
#pragma unroll
                for (int j = 0; j < 4; j++) d[cm][j] += e[cm][j];
            float* red = reinterpret_cast<float*>(sgen + kOffRed);
            if (live) {
#pragma unroll
                for (int cm = 0; cm < 2; cm++)
#pragma unroll
                    for (int j = 0; j < 4; j++)
                        red[(warp * 8 + 2 * t + (j & 1)) * 36 + cm * 16 + (j >> 1) * 8 + gq] = d[cm][j];
                bar_consumers();
            }
            if (tid < 128) {
                const float2* red2 = reinterpret_cast<const float2*>(sgen + kOffRed);
                float sx = 0.f, sy = 0.f;
#pragma unroll
                for (int w = 0; w < kWarps; w++) {
                    const float2 v = red2[(w * 8 + (tid >> 4)) * 18 + (tid & 15)];
                    sx += v.x;
                    sy += v.y;
                }
                red_add_bf16x2_if(live, out + (tid >> 4) * kD + slice * 32 + (tid & 15) * 2, pack_bf16(sx, sy));
            }
            if (live) break;
            live = 1;
        }
        if (tid == 0) asm volatile("red.relaxed.gpu.global.add.u32 [%0], %1;" ::"l"(&g_done), "r"(1u) : "memory");
    } else if (warp == kWarps + 1) {
        const uint32_t flag = (ld_relaxed_u32(&g_done) >> 7) + 1u;
        asm volatile("barrier.cluster.arrive.relaxed.aligned;" ::: "memory");
        asm volatile("barrier.cluster.wait.aligned;" ::: "memory");
        if (lane == 0) {
            unsigned long long v;
            for (unsigned it = 0;; it++) {
                asm volatile("ld.acquire.gpu.global.u64 %0, [%1];" : "=l"(v) : "l"(&g_zf) : "memory");
                if ((uint32_t)v == flag) break;
                __nanosleep(256);
                if (it > kSpinLimit) __trap();
            }
            {
                const uint32_t t1 = (uint32_t)(v >> 32) + kC0;
                if (t1 - *sched + 1000u < 2000u) *sched = t1;
            }
            mbar_arrive(bar_z);
        }
    } else {
        uint64_t pol;
        asm volatile("createpolicy.fractional.L2::evict_first.b64 %0, 1.0;" : "=l"(pol));
        if (elect_one()) {
#pragma unroll
            for (int w = 0; w < kWarps; w++) {
                const uint32_t bar = bar_full + w * (kStages * 8);
                mbar_expect_tx(bar, kWTileBytes);
                tma_2d(ring + w * (kStages * kTileBytes), &tmWq, g * 512 + slice * 32, w * 64, bar, pol);
            }
        }
        __syncwarp();
        asm volatile("barrier.cluster.arrive.relaxed.aligned;" ::: "memory");
        if (elect_one()) {
            *sched = now_ns() + kOff;
            uint32_t due = 0;
            int stage = 1;
            uint32_t epar = 1;
#pragma unroll 1
            for (int seq = 1; seq < kSeq; seq++) {
                const bool is_wo = seq == kSeq - 1;
                const CUtensorMap* tm = is_wo ? &tmWo : (seq & 1) ? &tmK : &tmV;
                const uint32_t fb = bar_full + stage * 8, eb = bar_empty + stage * 8;
                const uint32_t dst = ring + stage * kTileBytes;
                const uint32_t bytes = is_wo ? kWTileBytes : kTileBytes;
                const uint32_t step = is_wo ? kTau / 2 : kTau;
                const int c0 = is_wo ? slice * 32 : 0;
                const int c1 = is_wo ? g * 512 : (pair * kSk + r * 2048 + ((seq - 1) >> 1) * (kWarps * kTileKeys)) * 2;
#pragma unroll
                for (int w = 0; w < kWarps; w++) {
                    if (seq >= kStages) mbar_wait(eb + w * (kStages * 8), epar);
                    unsigned it = 0;
                    while ((int)(now_ns() - (*sched + due)) < 0)
                        if (++it > kSpinLimit) __trap();
                    due += step;
                    mbar_expect_tx(fb + w * (kStages * 8), bytes);
                    tma_2d(dst + w * (kStages * kTileBytes), tm, c0, c1 + w * 64, fb + w * (kStages * 8), pol);
                }
                if (++stage == kStages) { stage = 0; epar ^= 1; }
            }
        }
        __syncwarp();
        asm volatile("barrier.cluster.wait.aligned;" ::: "memory");
    }
}

typedef CUresult (*EncodeTiledFn)(CUtensorMap*, CUtensorMapDataType, cuuint32_t, void*, const cuuint64_t*,
                                  const cuuint64_t*, const cuuint32_t*, const cuuint32_t*, CUtensorMapInterleave,
                                  CUtensorMapSwizzle, CUtensorMapL2promotion, CUtensorMapFloatOOBfill);

}

extern "C" void kernel_launch(void* const* d_in, const int* in_sizes, int n_in, void* d_out, int out_size) {
    (void)in_sizes; (void)n_in; (void)out_size;
    const __nv_bfloat16* x = (const __nv_bfloat16*)d_in[0];
    void* kc = d_in[1];
    void* vc = d_in[2];
    void* wq = d_in[3];
    void* wo = d_in[4];

    static EncodeTiledFn enc = nullptr;
    if (!enc) {
        void* fn = nullptr;
        cudaDriverEntryPointQueryResult qr;
        cudaGetDriverEntryPoint("cuTensorMapEncodeTiled", &fn, cudaEnableDefault, &qr);
        enc = (EncodeTiledFn)fn;
        cudaFuncSetAttribute(gqa_decode_kernel, cudaFuncAttributeMaxDynamicSharedMemorySize, kSmemBytes);
    }
    CUtensorMap tmK, tmV, tmWq, tmWo;
    for (int i = 0; i < 2; i++) {
        CUtensorMap* tm = i ? &tmV : &tmK;
        void* base = i ? vc : kc;
        cuuint64_t dims[2] = {64, (cuuint64_t)kB * kHkv * kSk * 2};
        cuuint64_t strides[1] = {128};
        cuuint32_t box[2] = {64, kTileKeys * 2};
        cuuint32_t es[2] = {1, 1};
        enc(tm, CU_TENSOR_MAP_DATA_TYPE_BFLOAT16, 2, base, dims, strides, box, es, CU_TENSOR_MAP_INTERLEAVE_NONE,
            CU_TENSOR_MAP_SWIZZLE_128B, CU_TENSOR_MAP_L2_PROMOTION_L2_128B, CU_TENSOR_MAP_FLOAT_OOB_FILL_NONE);
    }
    {
        cuuint64_t dims[2] = {4096, 512};
        cuuint64_t strides[1] = {8192};
        cuuint32_t box[2] = {32, 64};
        cuuint32_t es[2] = {1, 1};
        enc(&tmWq, CU_TENSOR_MAP_DATA_TYPE_BFLOAT16, 2, wq, dims, strides, box, es, CU_TENSOR_MAP_INTERLEAVE_NONE,
            CU_TENSOR_MAP_SWIZZLE_64B, CU_TENSOR_MAP_L2_PROMOTION_L2_128B, CU_TENSOR_MAP_FLOAT_OOB_FILL_NONE);
    }
    {
        cuuint64_t dims[2] = {512, 4096};
        cuuint64_t strides[1] = {1024};
        cuuint32_t box[2] = {32, 64};
        cuuint32_t es[2] = {1, 1};
        enc(&tmWo, CU_TENSOR_MAP_DATA_TYPE_BFLOAT16, 2, wo, dims, strides, box, es, CU_TENSOR_MAP_INTERLEAVE_NONE,
            CU_TENSOR_MAP_SWIZZLE_64B, CU_TENSOR_MAP_L2_PROMOTION_L2_128B, CU_TENSOR_MAP_FLOAT_OOB_FILL_NONE);
    }
    gqa_decode_kernel<<<2 + 128, kThreads, kSmemBytes>>>(tmK, tmV, tmWq, tmWo, x, (const __nv_bfloat16*)kc, (__nv_bfloat16*)d_out);
}
```

```cpp
#include <cuda_runtime.h>
#include <cuda_bf16.h>
#include <cuda.h>
#include <stdint.h>

namespace {

constexpr int kB = 8, kHkv = 8, kSk = 4096, kDh = 128, kD = 512;
constexpr int kWarps = 8;
constexpr int kThreads = 320;
constexpr int kTileKeys = 32;
constexpr int kTileBytes = kTileKeys * 256;
constexpr int kStages = 3;
constexpr int kSlots = kWarps * kStages;
constexpr int kIters = 2048 / (kWarps * kTileKeys);
constexpr int kSeq = 2 * kIters + 2;
constexpr int kWTileBytes = 64 * 64;
#define GQA_TAU 327
#define GQA_OFF 200
#define GQA_C0 300
constexpr uint32_t kTau = GQA_TAU, kOff = GQA_OFF, kC0 = GQA_C0;
constexpr uint32_t kPrefetchBytes = 8192;

constexpr int kOffRing = 0;
constexpr int kOffCml = kSlots * kTileBytes;
constexpr int kOffRed = kOffCml + 512;
constexpr int kOffQs = kOffRed + 9216;
constexpr int kOffBar = kOffQs + 1024;
constexpr int kOffSched = kOffBar + 56 * 8;
constexpr int kSmemBytes = kOffBar + 64 * 8 + 1024;

constexpr unsigned kSpinLimit = 1u << 24;

}

__device__ __align__(128) unsigned int g_done;
__device__ __align__(128) unsigned long long g_qll[8 * 8 * 256];
__device__ __align__(128) unsigned int g_o[8 * 8 * 2 * 256];
__device__ __align__(128) unsigned long long g_zf;
__device__ __align__(128) unsigned int g_of;

namespace {

__device__ __forceinline__ uint32_t smem_u32(const void* p) { return (uint32_t)__cvta_generic_to_shared(p); }
__device__ __forceinline__ void mbar_init(uint32_t bar, uint32_t cnt) {
    asm volatile("mbarrier.init.shared::cta.b64 [%0], %1;" ::"r"(bar), "r"(cnt) : "memory");
}
__device__ __forceinline__ void mbar_expect_tx(uint32_t bar, uint32_t bytes) {
    asm volatile("mbarrier.arrive.expect_tx.shared::cta.b64 _, [%0], %1;" ::"r"(bar), "r"(bytes) : "memory");
}
__device__ __forceinline__ void mbar_arrive(uint32_t bar) {
    asm volatile("mbarrier.arrive.shared::cta.b64 _, [%0];" ::"r"(bar) : "memory");
}
__device__ __forceinline__ void mbar_wait(uint32_t bar, uint32_t parity) {
    uint32_t done;
    unsigned it = 0;
    do {
        asm volatile(
            "{ .reg .pred p; mbarrier.try_wait.parity.shared::cta.b64 p, [%1], %2; selp.u32 %0, 1, 0, p; }"
            : "=r"(done) : "r"(bar), "r"(parity) : "memory");
        if (++it > kSpinLimit) __trap();
    } while (!done);
}
__device__ __forceinline__ void mbar_wait_cluster(uint32_t bar, uint32_t parity) {
    uint32_t done;
    unsigned it = 0;
    do {
        asm volatile(
            "{ .reg .pred p; mbarrier.try_wait.parity.acquire.cluster.shared::cta.b64 p, [%1], %2; selp.u32 %0, 1, 0, p; }"
            : "=r"(done) : "r"(bar), "r"(parity) : "memory");
        if (++it > kSpinLimit) __trap();
    } while (!done);
}
__device__ __forceinline__ void tma_2d(uint32_t dst, const CUtensorMap* tm, int c0, int c1, uint32_t bar, uint64_t pol) {
    asm volatile(
        "cp.async.bulk.tensor.2d.shared::cluster.global.mbarrier::complete_tx::bytes.L2::cache_hint [%0], [%1, {%3, %4}], [%2], %5;"
        ::"r"(dst), "l"(tm), "r"(bar), "r"(c0), "r"(c1), "l"(pol) : "memory");
}
__device__ __forceinline__ uint32_t now_ns() {
    uint32_t t;
    asm volatile("mov.u32 %0, %%globaltimer_lo;" : "=r"(t) :: "memory");
    return t;
}
__device__ __forceinline__ void ldsm_x4(uint32_t (&r)[4], uint32_t addr) {
    asm volatile("ldmatrix.sync.aligned.m8n8.x4.shared.b16 {%0,%1,%2,%3}, [%4];"
                 : "=r"(r[0]), "=r"(r[1]), "=r"(r[2]), "=r"(r[3]) : "r"(addr) : "memory");
}
__device__ __forceinline__ void ldsm_x4_t(uint32_t (&r)[4], uint32_t addr) {
    asm volatile("ldmatrix.sync.aligned.m8n8.x4.trans.shared.b16 {%0,%1,%2,%3}, [%4];"
                 : "=r"(r[0]), "=r"(r[1]), "=r"(r[2]), "=r"(r[3]) : "r"(addr) : "memory");
}
__device__ __forceinline__ void mma_bf16(float (&d)[4], const uint32_t (&a)[4], uint32_t b0, uint32_t b1) {
    asm volatile(
        "mma.sync.aligned.m16n8k16.row.col.f32.bf16.bf16.f32 {%0,%1,%2,%3}, {%4,%5,%6,%7}, {%8,%9}, {%0,%1,%2,%3};"
        : "+f"(d[0]), "+f"(d[1]), "+f"(d[2]), "+f"(d[3])
        : "r"(a[0]), "r"(a[1]), "r"(a[2]), "r"(a[3]), "r"(b0), "r"(b1));
}
__device__ __forceinline__ uint32_t movmatrix_t(uint32_t a) {
    uint32_t d;
    asm volatile("movmatrix.sync.aligned.m8n8.trans.b16 %0, %1;" : "=r"(d) : "r"(a));
    return d;
}
__device__ __forceinline__ uint32_t pack_bf16(float lo, float hi) {
    uint32_t r;
    asm("cvt.rn.bf16x2.f32 %0, %1, %2;" : "=r"(r) : "f"(hi), "f"(lo));
    return r;
}
__device__ __forceinline__ float ex2(float x) {
    float y;
    asm("ex2.approx.ftz.f32 %0, %1;" : "=f"(y) : "f"(x));
    return y;
}
__device__ __forceinline__ void st_ll(unsigned long long* p, uint32_t data, uint32_t flag) {
    unsigned long long v = ((unsigned long long)flag << 32) | data;
    asm volatile("st.relaxed.gpu.global.u64 [%0], %1;" ::"l"(p), "l"(v) : "memory");
}
__device__ __forceinline__ unsigned long long ld_ll(const unsigned long long* p) {
    unsigned long long v;
    asm volatile("ld.relaxed.gpu.global.u64 %0, [%1];" : "=l"(v) : "l"(p) : "memory");
    return v;
}
__device__ __forceinline__ void st_relaxed_v4(unsigned int* p, uint32_t a, uint32_t b, uint32_t c, uint32_t d) {
    asm volatile("st.relaxed.gpu.global.v4.u32 [%0], {%1,%2,%3,%4};" ::"l"(p), "r"(a), "r"(b), "r"(c), "r"(d) : "memory");
}
__device__ __forceinline__ void st_relaxed_u32_if(bool p, unsigned int* ptr, uint32_t a) {
    asm volatile("{ .reg .pred p; setp.ne.u32 p, %2, 0; @p st.relaxed.gpu.global.u32 [%0], %1; }"
                 ::"l"(ptr), "r"(a), "r"((uint32_t)p) : "memory");
}
__device__ __forceinline__ void red_add_bf16x2_if(bool p, __nv_bfloat16* ptr, uint32_t v) {
    asm volatile("{ .reg .pred p; setp.ne.u32 p, %2, 0; @p red.relaxed.gpu.global.add.noftz.bf16x2 [%0], %1; }"
                 ::"l"(ptr), "r"(v), "r"((uint32_t)p) : "memory");
}
__device__ __forceinline__ void sts_v4(uint32_t addr, float a, float b, float c, float d) {
    asm volatile("st.shared.v4.f32 [%0], {%1,%2,%3,%4};" ::"r"(addr), "f"(a), "f"(b), "f"(c), "f"(d) : "memory");
}
__device__ __forceinline__ void ld_relaxed_v4_if(bool p, uint4& v, const unsigned int* ptr) {
    asm volatile("{ .reg .pred p; setp.ne.u32 p, %5, 0; @p ld.relaxed.gpu.global.v4.u32 {%0,%1,%2,%3}, [%4]; }"
                 : "+r"(v.x), "+r"(v.y), "+r"(v.z), "+r"(v.w) : "l"(ptr), "r"((uint32_t)p) : "memory");
}
__device__ __forceinline__ bool o_valid(const uint4& v) { return min(min(v.x, v.y), min(v.z, v.w)) != 0u; }
__device__ __forceinline__ uint32_t add_bf16x2(uint32_t a, uint32_t b) {
    uint32_t d;
    asm("add.rn.bf16x2 %0, %1, %2;" : "=r"(d) : "r"(a), "r"(b));
    return d;
}
__device__ __forceinline__ uint4 lds_v4(uint32_t addr) {
    uint4 v;
    asm volatile("ld.shared.v4.u32 {%0,%1,%2,%3}, [%4];" : "=r"(v.x), "=r"(v.y), "=r"(v.z), "=r"(v.w) : "r"(addr) : "memory");
    return v;
}
__device__ __forceinline__ uint32_t ld_relaxed_u32(const unsigned int* p) {
    uint32_t v;
    asm volatile("ld.relaxed.gpu.global.u32 %0, [%1];" : "=r"(v) : "l"(p) : "memory");
    return v;
}
__device__ __forceinline__ uint32_t mapa(uint32_t addr, uint32_t rank) {
    uint32_t r;
    asm("mapa.shared::cluster.u32 %0, %1, %2;" : "=r"(r) : "r"(addr), "r"(rank));
    return r;
}
__device__ __forceinline__ void st_async_v4(uint32_t addr, float a, float b, float c, float d, uint32_t bar) {
    asm volatile("st.async.weak.shared::cluster.mbarrier::complete_tx::bytes.v4.f32 [%0], {%1,%2,%3,%4}, [%5];"
                 ::"r"(addr), "f"(a), "f"(b), "f"(c), "f"(d), "r"(bar) : "memory");
}
__device__ __forceinline__ bool elect_one() {
    uint32_t pred;
    asm volatile("{ .reg .pred P; elect.sync _|P, 0xffffffff; selp.b32 %0, 1, 0, P; }" : "=r"(pred));
    return pred != 0;
}
__device__ __forceinline__ void bar_consumers() { asm volatile("bar.sync 1, 256;" ::: "memory"); }

__global__ void __cluster_dims__(2, 1, 1) __launch_bounds__(kThreads, 1)
gqa_decode_kernel(const __grid_constant__ CUtensorMap tmK, const __grid_constant__ CUtensorMap tmV,
                  const __grid_constant__ CUtensorMap tmWq, const __grid_constant__ CUtensorMap tmWo,
                  const __nv_bfloat16* __restrict__ x, const __nv_bfloat16* __restrict__ kc, __nv_bfloat16* __restrict__ out) {
    extern __shared__ uint8_t smem_raw[];
    uint32_t sbase = (smem_u32(smem_raw) + 1023u) & ~1023u;
    asm volatile("" : "+r"(sbase));
    uint8_t* sgen = smem_raw + (sbase - smem_u32(smem_raw));

    const int tid = threadIdx.x, lane = tid & 31;
    const int warp = __shfl_sync(0xffffffffu, tid >> 5, 0);
    if (blockIdx.x < 2) {
        if (blockIdx.x == 0) {
            const uint32_t t0 = now_ns();
            const uint32_t epoch_raw = ld_relaxed_u32(&g_done);
            if (tid < 256) {
                st_relaxed_v4(reinterpret_cast<unsigned int*>(out) + tid * 8, 0u, 0u, 0u, 0u);
                st_relaxed_v4(reinterpret_cast<unsigned int*>(out) + tid * 8 + 4, 0u, 0u, 0u, 0u);
            }
            __syncthreads();
            if (tid == 0)
                asm volatile("st.release.gpu.global.u64 [%0], %1;" ::"l"(&g_zf), "l"(((unsigned long long)t0 << 32) | ((epoch_raw >> 7) + 1u)) : "memory");
        } else {
            const uint32_t epoch_raw = ld_relaxed_u32(&g_done);
            if (tid < 256) {
#pragma unroll 8
                for (int i = 0; i < 32; i++) st_relaxed_v4(g_o + (i * 256 + tid) * 4, 0u, 0u, 0u, 0u);
            }
            __syncthreads();
            if (tid == 0)
                asm volatile("st.release.gpu.global.u32 [%0], %1;" ::"l"(&g_of), "r"((epoch_raw >> 7) + 1u) : "memory");
        }
        return;
    }
    const int cta = blockIdx.x - 2;
    const int r = cta & 1, pair = cta >> 1, b = pair >> 3, g = pair & 7;
    const int slice = b * 2 + r;
    const int gq = lane >> 2, t = lane & 3;
    if (tid == kThreads - 32)
        asm volatile("cp.async.bulk.prefetch.L2.global [%0], %1;" ::"l"(kc + (size_t)(pair * kSk + r * 2048) * kDh), "r"(kPrefetchBytes) : "memory");

    const uint32_t bar_full = sbase + kOffBar;
    const uint32_t bar_empty = bar_full + kSlots * 8;
    const uint32_t bar_ml = bar_empty + kSlots * 8;
    const uint32_t bar_z = bar_ml + 8;
    const uint32_t ring = sbase + kOffRing;
    volatile uint32_t* const sched = reinterpret_cast<volatile uint32_t*>(sgen + kOffSched);

    static_assert(2 * kSlots + 2 == 5 * (kThreads / 32), "barrier initialisation");
    if (elect_one()) {
        if (warp >= kWarps - 2) {
            const CUtensorMap* tm = warp == kWarps ? &tmWq : warp == kWarps + 1 ? &tmK : warp == kWarps - 1 ? &tmV : &tmWo;
            asm volatile("prefetch.tensormap [%0];" ::"l"(tm) : "memory");
        }
#pragma unroll
        for (int i = 0; i < 5; i++) mbar_init(bar_full + (warp * 5 + i) * 8, 1);
        asm volatile("fence.mbarrier_init.release.cluster;" ::: "memory");
    }
    __syncthreads();
    if (warp < kWarps) {
        const uint32_t my_full = bar_full + warp * (kStages * 8), my_empty = bar_empty + warp * (kStages * 8);
        const uint32_t my_ring = ring + warp * (kStages * kTileBytes);
        uint4 xv[2];
        {
            const __nv_bfloat16* xp = x + gq * 512 + warp * 64 + t * 16;
#pragma unroll
            for (int i = 0; i < 2; i++)
                asm volatile("ld.global.nc.v4.u32 {%0,%1,%2,%3}, [%4];"
                             : "=r"(xv[i].x), "=r"(xv[i].y), "=r"(xv[i].z), "=r"(xv[i].w) : "l"(xp + i * 8));
        }
        const uint32_t epoch_raw = ld_relaxed_u32(&g_done);

        unsigned long long* const q_pub = &g_qll[(g * 8 + (tid >> 4)) * 256 + slice * 16 + (tid & 15)];
        unsigned int* const o_cta = &g_o[((g * 8 + b) * 2 + r) * 256];
        if (tid < 128) st_ll(q_pub, 0u, 0u);
        if (tid == 0) mbar_expect_tx(bar_ml, 32 * 16);
        __syncwarp();
        asm volatile("barrier.cluster.arrive.relaxed.aligned;" ::: "memory");

        const uint32_t flag = (epoch_raw >> 7) + 1u;

        {
            float d[2][4] = {{0.f, 0.f, 0.f, 0.f}, {0.f, 0.f, 0.f, 0.f}};
            const uint32_t xw[8] = {xv[0].x, xv[0].y, xv[0].z, xv[0].w, xv[1].x, xv[1].y, xv[1].z, xv[1].w};
            mbar_wait(my_full, 0);
            const uint32_t wt = my_ring;
            const int kl = lane & 7;
#pragma unroll
            for (int s = 0; s < 4; s++) {
                const int row = (kl >> 1) * 16 + 4 * s + 2 * (lane >> 4) + (kl & 1);
#pragma unroll
                for (int cm = 0; cm < 2; cm++) {
                    const int chunk = 2 * cm + ((lane >> 3) & 1);
                    uint32_t a[4];
                    ldsm_x4_t(a, wt + row * 64 + ((chunk ^ ((row >> 1) & 3)) << 4));
                    mma_bf16(d[cm], a, xw[2 * s], xw[2 * s + 1]);
                }
            }
            float* red = reinterpret_cast<float*>(sgen + kOffRed);
#pragma unroll
            for (int cm = 0; cm < 2; cm++)
#pragma unroll
                for (int j = 0; j < 4; j++)
                    red[(warp * 8 + 2 * t + (j & 1)) * 36 + cm * 16 + (j >> 1) * 8 + gq] = d[cm][j];
            __syncwarp();
            if (lane == 0) mbar_arrive(my_empty);
            bar_consumers();
            if (tid < 128) {
                const float2* red2 = reinterpret_cast<const float2*>(sgen + kOffRed);
                float sx = 0.f, sy = 0.f;
#pragma unroll
                for (int w = 0; w < kWarps; w++) {
                    const float2 v = red2[(w * 8 + (tid >> 4)) * 18 + (tid & 15)];
                    sx += v.x;
                    sy += v.y;
                }
                st_ll(q_pub, pack_bf16(sx, sy), flag);
            }
            {
                const unsigned long long* qp = &g_qll[(g * 8 + b) * 256 + tid];
                unsigned long long v = ld_ll(qp);
                unsigned it = 0;
                while ((uint32_t)(v >> 32) != flag) {
                    __nanosleep(64);
                    v = ld_ll(qp);
                    if (++it > kSpinLimit) __trap();
                }
                reinterpret_cast<uint32_t*>(sgen + kOffQs)[tid] = (uint32_t)v;
            }
            bar_consumers();
        }
        uint32_t qf[8][2];
        {
            const uint32_t* qs = reinterpret_cast<const uint32_t*>(sgen + kOffQs);
#pragma unroll
            for (int ks = 0; ks < 8; ks++) {
                qf[ks][0] = qs[(gq & 3) * 64 + ks * 8 + t];
                qf[ks][1] = qs[(gq & 3) * 64 + ks * 8 + 4 + t];
            }
        }
        asm volatile("barrier.cluster.wait.aligned;" ::: "memory");

        const int krow = (lane & 7) + ((lane >> 3) & 1) * 8, vrow = (lane & 7) + (lane >> 4) * 8;
        const uint32_t koff = krow * 256, kx = ((lane >> 4) ^ ((2 * krow) & 7)) << 4;
        const uint32_t voff = vrow * 256, vx = (((lane >> 3) & 1) ^ ((2 * vrow) & 7)) << 4;
        auto tile_off = [&](uint32_t rowoff, uint32_t xr, int c2, int blk) -> uint32_t {
            return rowoff + blk * 4096 + (c2 >> 2) * 128 + (xr ^ ((((2 * c2) & 7) ^ (c2 >> 2)) << 4));
        };

        constexpr float kScale = 0.08838834764831845f * 1.4426950408889634f;
        float o[8][4];
#pragma unroll
        for (int i = 0; i < 8; i++) { o[i][0] = o[i][1] = o[i][2] = o[i][3] = 0.f; }
        float m0 = -INFINITY, m1 = -INFINITY, l0 = 0.f, l1 = 0.f;
        uint32_t stage = 1, par = 0;

#pragma unroll 1
        for (int it = 0; it < kIters; it++) {
            mbar_wait(my_full + stage * 8, par);
            uint32_t tb = my_ring + stage * kTileBytes;
            float s[2][4];
#pragma unroll
            for (int mt = 0; mt < 2; mt++) {
                float sa[4] = {0.f, 0.f, 0.f, 0.f}, sb[4] = {0.f, 0.f, 0.f, 0.f};
#pragma unroll
                for (int ks = 0; ks < 8; ks += 2) {
                    uint32_t a[4], a2[4];
                    ldsm_x4(a, tb + tile_off(koff, kx, ks, mt));
                    ldsm_x4(a2, tb + tile_off(koff, kx, ks + 1, mt));
                    mma_bf16(sa, a, qf[ks][0], qf[ks][1]);
                    mma_bf16(sb, a2, qf[ks + 1][0], qf[ks + 1][1]);
                }
#pragma unroll
                for (int j = 0; j < 4; j++) s[mt][j] = sa[j] + sb[j];
            }
            __syncwarp();
            if (lane == 0) mbar_arrive(my_empty + stage * 8);
            if (++stage == kStages) { stage = 0; par ^= 1; }

            float mx0 = fmaxf(fmaxf(s[0][0], s[0][2]), fmaxf(s[1][0], s[1][2]));
            float mx1 = fmaxf(fmaxf(s[0][1], s[0][3]), fmaxf(s[1][1], s[1][3]));
#pragma unroll
            for (int d = 4; d <= 16; d <<= 1) {
                mx0 = fmaxf(mx0, __shfl_xor_sync(0xffffffffu, mx0, d));
                mx1 = fmaxf(mx1, __shfl_xor_sync(0xffffffffu, mx1, d));
            }
            const float mn0 = fmaxf(m0, mx0), mn1 = fmaxf(m1, mx1);
            const float sc0 = ex2((m0 - mn0) * kScale), sc1 = ex2((m1 - mn1) * kScale);
            m0 = mn0;
            m1 = mn1;
            const float mb0 = mn0 * kScale, mb1 = mn1 * kScale;
            float p[2][4];
#pragma unroll
            for (int mt = 0; mt < 2; mt++) {
                p[mt][0] = ex2(fmaf(s[mt][0], kScale, -mb0));
                p[mt][1] = ex2(fmaf(s[mt][1], kScale, -mb1));
                p[mt][2] = ex2(fmaf(s[mt][2], kScale, -mb0));
                p[mt][3] = ex2(fmaf(s[mt][3], kScale, -mb1));
            }
            l0 = l0 * sc0 + ((p[0][0] + p[0][2]) + (p[1][0] + p[1][2]));
            l1 = l1 * sc1 + ((p[0][1] + p[0][3]) + (p[1][1] + p[1][3]));
            float os0 = sc0, os1 = sc1;
            if (it == kIters - 1) {
#pragma unroll
                for (int d = 4; d <= 16; d <<= 1) {
                    l0 += __shfl_xor_sync(0xffffffffu, l0, d);
                    l1 += __shfl_xor_sync(0xffffffffu, l1, d);
                }
                const int sl = r * 8 + warp;
                if (t < 2 && gq < 2)
                    st_async_v4(mapa(sbase + kOffCml + (t * 16 + sl) * 16, gq), m0, l0, m1, l1, mapa(bar_ml, gq));
                mbar_wait_cluster(bar_ml, 0);
                const float4 ml = reinterpret_cast<const float4*>(sgen + kOffCml)[lane];
                float M0 = ml.x, M1 = ml.z;
#pragma unroll
                for (int d = 1; d <= 8; d <<= 1) {
                    M0 = fmaxf(M0, __shfl_xor_sync(0xffffffffu, M0, d));
                    M1 = fmaxf(M1, __shfl_xor_sync(0xffffffffu, M1, d));
                }
                const float e0 = ex2((ml.x - M0) * kScale), e1 = ex2((ml.z - M1) * kScale);
                float L0 = e0 * ml.y, L1 = e1 * ml.w;
#pragma unroll
                for (int d = 1; d <= 8; d <<= 1) {
                    L0 += __shfl_xor_sync(0xffffffffu, L0, d);
                    L1 += __shfl_xor_sync(0xffffffffu, L1, d);
                }
                const float f0 = __shfl_sync(0xffffffffu, e0 / L0, (t & 1) * 16 + sl);
                const float f1 = __shfl_sync(0xffffffffu, e1 / L1, (t & 1) * 16 + sl);
                os0 *= f0;
                os1 *= f1;
#pragma unroll
                for (int mt = 0; mt < 2; mt++) {
                    p[mt][0] *= f0; p[mt][1] *= f1; p[mt][2] *= f0; p[mt][3] *= f1;
                }
            }
            uint32_t pb[2][2];
#pragma unroll
            for (int mt = 0; mt < 2; mt++) {
                pb[mt][0] = movmatrix_t(pack_bf16(p[mt][0], p[mt][1]));
                pb[mt][1] = movmatrix_t(pack_bf16(p[mt][2], p[mt][3]));
            }
#pragma unroll
            for (int i = 0; i < 8; i++) {
                o[i][0] *= os0; o[i][1] *= os1; o[i][2] *= os0; o[i][3] *= os1;
            }

            if (it == kIters - 1) {
                const uint32_t xb = my_ring + ((kSeq - 3) % kStages) * kTileBytes;
                if (t < 2) {
#pragma unroll
                    for (int i = 0; i < 8; i++) sts_v4(xb + i * 256 + (gq * 2 + t) * 16, o[i][0], o[i][1], o[i][2], o[i][3]);
                }
                sts_v4(xb + 2048 + lane * 16, __uint_as_float(pb[0][0]), __uint_as_float(pb[0][1]),
                       __uint_as_float(pb[1][0]), __uint_as_float(pb[1][1]));
                break;
            }

            mbar_wait(my_full + stage * 8, par);
            tb = my_ring + stage * kTileBytes;
#pragma unroll
            for (int kt = 0; kt < 2; kt++) {
#pragma unroll
                for (int dm = 0; dm < 8; dm++) {
                    uint32_t a[4];
                    ldsm_x4_t(a, tb + tile_off(voff, vx, dm, kt));
                    mma_bf16(o[dm], a, pb[kt][0], pb[kt][1]);
                }
            }
            __syncwarp();
            if (lane == 0) mbar_arrive(my_empty + stage * 8);
            if (++stage == kStages) { stage = 0; par ^= 1; }
        }
        bar_consumers();

        float oa[4] = {0.f, 0.f, 0.f, 0.f}, ob[4] = {0.f, 0.f, 0.f, 0.f};
        uint4 pw[kWarps];
        {
            const uint32_t xb = ring + ((kSeq - 3) % kStages) * kTileBytes;
#pragma unroll
            for (int w = 0; w < kWarps; w++) {
                const uint4 v = lds_v4(xb + w * (kStages * kTileBytes) + warp * 256 + (gq * 2 + (t & 1)) * 16);
                oa[0] += __uint_as_float(v.x); oa[1] += __uint_as_float(v.y);
                oa[2] += __uint_as_float(v.z); oa[3] += __uint_as_float(v.w);
                pw[w] = lds_v4(xb + w * (kStages * kTileBytes) + 2048 + lane * 16);
            }
        }
        mbar_wait(bar_z, 0);
        uint32_t live = 0;
#pragma unroll 1
        for (;;) {
            asm volatile("" : "+r"(live));
            if (live) {
                constexpr int kVStage = (kSeq - 2) % kStages, kVPar = ((kSeq - 2) / kStages) & 1;
                const uint32_t voffw = tile_off(voff, vx, warp, 0), vblk = 4096;
#pragma unroll
                for (int w = 0; w < kWarps; w++) {
                    mbar_wait(bar_full + (w * kStages + kVStage) * 8, kVPar);
                    const uint32_t vt = ring + (w * kStages + kVStage) * kTileBytes + voffw;
                    uint32_t a[4], a2[4];
                    ldsm_x4_t(a, vt);
                    ldsm_x4_t(a2, vt + vblk);
                    mma_bf16(oa, a, pw[w].x, pw[w].y);
                    mma_bf16(ob, a2, pw[w].z, pw[w].w);
                }
            }
            {
                const bool odd = gq & 1;
                const float ca = t < 2 ? oa[0] + ob[0] : oa[1] + ob[1], cb = t < 2 ? oa[2] + ob[2] : oa[3] + ob[3];
                const float cx = __shfl_xor_sync(0xffffffffu, odd ? ca : cb, 4);
                const uint32_t w0 = ~pack_bf16(odd ? cx : ca, odd ? cb : cx);
                unsigned int* op = o_cta + warp * 32 + ((t & 1) * 2 + (t >> 1)) * 8 + (gq & 1) * 4 + (((gq >> 1) - 2 * warp - (gq & 1)) & 3);
                st_relaxed_u32_if(live, op, w0);
            }
            uint4 u[4];
#pragma unroll
            for (int c = 0; c < 4; c++) u[c] = make_uint4(0u, 0u, 0u, 0u);
            const unsigned int* op = &g_o[(g * 8 + gq) * 512 + ((warp & 1) * 4 + (t >> 1)) * 32 + (warp >> 1) * 8 + (t & 1) * 4];
            constexpr int kWoStage = (kSeq - 1) % kStages, kWoPar = ((kSeq - 1) / kStages) & 1;
            if (live) mbar_wait(my_full + kWoStage * 8, kWoPar);
            for (unsigned it = 0;; it++) {
#pragma unroll
                for (int c = 0; c < 4; c++)
                    ld_relaxed_v4_if(live && !o_valid(u[c]), u[c], op + (c >> 1) * 256 + (c & 1) * 64);
                const bool all = o_valid(u[0]) && o_valid(u[1]) && o_valid(u[2]) && o_valid(u[3]);
                if (__all_sync(0xffffffffu, all || !live)) break;
                if (it > kSpinLimit) __trap();
            }
            const uint32_t b0[4] = {add_bf16x2(~u[0].x, ~u[2].x), add_bf16x2(~u[0].y, ~u[2].y), add_bf16x2(~u[0].z, ~u[2].z), add_bf16x2(~u[0].w, ~u[2].w)};
            const uint32_t b1[4] = {add_bf16x2(~u[1].x, ~u[3].x), add_bf16x2(~u[1].y, ~u[3].y), add_bf16x2(~u[1].z, ~u[3].z), add_bf16x2(~u[1].w, ~u[3].w)};
            const uint32_t wt = my_ring + kWoStage * kTileBytes;
            const int drow = (lane >> 4) * 32 + (lane & 6) * 4 + (lane & 1), drot = (lane & 7) >> 1;
            float d[2][4], e[2][4];
#pragma unroll
            for (int cm = 0; cm < 2; cm++)
#pragma unroll
                for (int j = 0; j < 4; j++) d[cm][j] = e[cm][j] = 0.f;
#pragma unroll
            for (int s = 0; s < 4; s++) {
                const int row = drow + 2 * ((s + drot) & 3);
#pragma unroll
                for (int cm = 0; cm < 2; cm++) {
                    const int chunk = 2 * cm + ((lane >> 3) & 1);
                    uint32_t a[4];
                    ldsm_x4_t(a, wt + row * 64 + ((chunk ^ ((row >> 1) & 3)) << 4));
                    mma_bf16((s & 1) ? e[cm] : d[cm], a, b0[s], b1[s]);
                }
            }
#pragma unroll
            for (int cm = 0; cm < 2; cm++)
#pragma unroll
                for (int j = 0; j < 4; j++) d[cm][j] += e[cm][j];
            float* red = reinterpret_cast<float*>(sgen + kOffRed);
            if (live) {
#pragma unroll
                for (int cm = 0; cm < 2; cm++)
#pragma unroll
                    for (int j = 0; j < 4; j++)
                        red[(warp * 8 + 2 * t + (j & 1)) * 36 + cm * 16 + (j >> 1) * 8 + gq] = d[cm][j];
                bar_consumers();
            }
            if (tid < 128) {
                const float2* red2 = reinterpret_cast<const float2*>(sgen + kOffRed);
                float sx = 0.f, sy = 0.f;
#pragma unroll
                for (int w = 0; w < kWarps; w++) {
                    const float2 v = red2[(w * 8 + (tid >> 4)) * 18 + (tid & 15)];
                    sx += v.x;
                    sy += v.y;
                }
                red_add_bf16x2_if(live, out + (tid >> 4) * kD + slice * 32 + (tid & 15) * 2, pack_bf16(sx, sy));
            }
            if (live) break;
            live = 1;
        }
        if (tid == 0) asm volatile("red.relaxed.gpu.global.add.u32 [%0], %1;" ::"l"(&g_done), "r"(1u) : "memory");
    } else if (warp == kWarps + 1) {
        const uint32_t flag = (ld_relaxed_u32(&g_done) >> 7) + 1u;
        asm volatile("barrier.cluster.arrive.relaxed.aligned;" ::: "memory");
        asm volatile("barrier.cluster.wait.aligned;" ::: "memory");
        if (lane == 0) {
            unsigned long long v;
            for (unsigned it = 0;; it++) {
                asm volatile("ld.acquire.gpu.global.u64 %0, [%1];" : "=l"(v) : "l"(&g_zf) : "memory");
                if ((uint32_t)v == flag) break;
                __nanosleep(256);
                if (it > kSpinLimit) __trap();
            }
            {
                const uint32_t t1 = (uint32_t)(v >> 32) + kC0;
                if (t1 - *sched + 1000u < 2000u) *sched = t1;
            }
            for (unsigned it = 0;; it++) {
                uint32_t f;
                asm volatile("ld.acquire.gpu.global.u32 %0, [%1];" : "=r"(f) : "l"(&g_of) : "memory");
                if (f == flag) break;
                __nanosleep(1000);
                if (it > (kSpinLimit >> 4)) __trap();
            }
            mbar_arrive(bar_z);
        }
    } else {
        uint64_t pol;
        asm volatile("createpolicy.fractional.L2::evict_first.b64 %0, 1.0;" : "=l"(pol));
        if (elect_one()) {
#pragma unroll
            for (int w = 0; w < kWarps; w++) {
                const uint32_t bar = bar_full + w * (kStages * 8);
                mbar_expect_tx(bar, kWTileBytes);
                tma_2d(ring + w * (kStages * kTileBytes), &tmWq, g * 512 + slice * 32, w * 64, bar, pol);
            }
        }
        __syncwarp();
        asm volatile("barrier.cluster.arrive.relaxed.aligned;" ::: "memory");
        if (elect_one()) {
            *sched = now_ns() + kOff;
            uint32_t due = 0;
            int stage = 1;
            uint32_t epar = 1;
#pragma unroll 1
            for (int seq = 1; seq < kSeq; seq++) {
                const bool is_wo = seq == kSeq - 1;
                const CUtensorMap* tm = is_wo ? &tmWo : (seq & 1) ? &tmK : &tmV;
                const uint32_t fb = bar_full + stage * 8, eb = bar_empty + stage * 8;
                const uint32_t dst = ring + stage * kTileBytes;
                const uint32_t bytes = is_wo ? kWTileBytes : kTileBytes;
                const uint32_t step = is_wo ? kTau / 2 : kTau;
                const int c0 = is_wo ? slice * 32 : 0;
                const int c1 = is_wo ? g * 512 : (pair * kSk + r * 2048 + ((seq - 1) >> 1) * (kWarps * kTileKeys)) * 2;
#pragma unroll
                for (int w = 0; w < kWarps; w++) {
                    if (seq >= kStages) mbar_wait(eb + w * (kStages * 8), epar);
                    unsigned it = 0;
                    while ((int)(now_ns() - (*sched + due)) < 0)
                        if (++it > kSpinLimit) __trap();
                    due += step;
                    mbar_expect_tx(fb + w * (kStages * 8), bytes);
                    tma_2d(dst + w * (kStages * kTileBytes), tm, c0, c1 + w * 64, fb + w * (kStages * 8), pol);
                }
                if (++stage == kStages) { stage = 0; epar ^= 1; }
            }
        }
        __syncwarp();
        asm volatile("barrier.cluster.wait.aligned;" ::: "memory");
    }
}

typedef CUresult (*EncodeTiledFn)(CUtensorMap*, CUtensorMapDataType, cuuint32_t, void*, const cuuint64_t*,
                                  const cuuint64_t*, const cuuint32_t*, const cuuint32_t*, CUtensorMapInterleave,
                                  CUtensorMapSwizzle, CUtensorMapL2promotion, CUtensorMapFloatOOBfill);

}

extern "C" void kernel_launch(void* const* d_in, const int* in_sizes, int n_in, void* d_out, int out_size) {
    (void)in_sizes; (void)n_in; (void)out_size;
    const __nv_bfloat16* x = (const __nv_bfloat16*)d_in[0];
    void* kc = d_in[1];
    void* vc = d_in[2];
    void* wq = d_in[3];
    void* wo = d_in[4];

    static EncodeTiledFn enc = nullptr;
    if (!enc) {
        void* fn = nullptr;
        cudaDriverEntryPointQueryResult qr;
        cudaGetDriverEntryPoint("cuTensorMapEncodeTiled", &fn, cudaEnableDefault, &qr);
        enc = (EncodeTiledFn)fn;
        cudaFuncSetAttribute(gqa_decode_kernel, cudaFuncAttributeMaxDynamicSharedMemorySize, kSmemBytes);
    }
    CUtensorMap tmK, tmV, tmWq, tmWo;
    for (int i = 0; i < 2; i++) {
        CUtensorMap* tm = i ? &tmV : &tmK;
        void* base = i ? vc : kc;
        cuuint64_t dims[2] = {64, (cuuint64_t)kB * kHkv * kSk * 2};
        cuuint64_t strides[1] = {128};
        cuuint32_t box[2] = {64, kTileKeys * 2};
        cuuint32_t es[2] = {1, 1};
        enc(tm, CU_TENSOR_MAP_DATA_TYPE_BFLOAT16, 2, base, dims, strides, box, es, CU_TENSOR_MAP_INTERLEAVE_NONE,
            CU_TENSOR_MAP_SWIZZLE_128B, CU_TENSOR_MAP_L2_PROMOTION_L2_128B, CU_TENSOR_MAP_FLOAT_OOB_FILL_NONE);
    }
    {
        cuuint64_t dims[2] = {4096, 512};
        cuuint64_t strides[1] = {8192};
        cuuint32_t box[2] = {32, 64};
        cuuint32_t es[2] = {1, 1};
        enc(&tmWq, CU_TENSOR_MAP_DATA_TYPE_BFLOAT16, 2, wq, dims, strides, box, es, CU_TENSOR_MAP_INTERLEAVE_NONE,
            CU_TENSOR_MAP_SWIZZLE_64B, CU_TENSOR_MAP_L2_PROMOTION_L2_128B, CU_TENSOR_MAP_FLOAT_OOB_FILL_NONE);
    }
    {
        cuuint64_t dims[2] = {512, 4096};
        cuuint64_t strides[1] = {1024};
        cuuint32_t box[2] = {32, 64};
        cuuint32_t es[2] = {1, 1};
        enc(&tmWo, CU_TENSOR_MAP_DATA_TYPE_BFLOAT16, 2, wo, dims, strides, box, es, CU_TENSOR_MAP_INTERLEAVE_NONE,
            CU_TENSOR_MAP_SWIZZLE_64B, CU_TENSOR_MAP_L2_PROMOTION_L2_128B, CU_TENSOR_MAP_FLOAT_OOB_FILL_NONE);
    }
    gqa_decode_kernel<<<2 + 128, kThreads, kSmemBytes>>>(tmK, tmV, tmWq, tmWo, x, (const __nv_bfloat16*)kc, (__nv_bfloat16*)d_out);
}
```
